```python
import torch

def _softmax(x, axis=-1):
    return torch.softmax(x, dim=axis)
def _gelu(x):
    return torch.nn.functional.gelu(x, approximate="tanh")
def _silu(x):
    return torch.nn.functional.silu(x)
def _sigmoid(x):
    return torch.sigmoid(x)
def _layernorm(x, axis=-1, eps=1e-5):
    m = x.mean(dim=axis, keepdim=True)
    v = x.var(dim=axis, keepdim=True, unbiased=False)
    return (x - m) / torch.sqrt(v + eps)
def _scatter_add(tgt, idx, src, axis=0):
    return tgt.clone().index_add_(axis, idx, src)
def _segment_sum(src, seg, n):
    out = torch.zeros((n,) + src.shape[1:], dtype=src.dtype)
    return out.index_add_(0, seg, src)
def _pad(x, pw):
    flat = tuple(v for pair in reversed(pw) for v in pair)
    return torch.nn.functional.pad(x, flat)

kernel_name = 'standalone__molecular_angular_gemnet__graph'

def setup_inputs():

    _w = (lambda a: (lambda t: t.to(torch.bfloat16) if t.is_floating_point() else t)(torch.as_tensor(a)))
    N, deg, De, L = 10000, 16, 16, 1
    E = N * deg
    T = E * deg
    NR = 8
    dist = torch.rand(E).to(float)
    angle = (torch.rand(T) * torch.pi).to(float)
    centers = torch.linspace(0.0, 1.0, NR).to(float)
    ang_freq = torch.arange(1, L + 1).to(float)
    return {
        "m": _w((lambda *s: torch.randn(*s, dtype=torch.bfloat16) * 0.05)(E, De)),
        "idx_in": _w((lambda lo, hi, *s: torch.randint(lo, hi, s))(0, E, T).to(torch.int64)),
        "idx_out": _w((lambda lo, hi, *s: torch.randint(lo, hi, s))(0, E, T).to(torch.int64)),
        "dist": _w(dist),
        "angle": _w(angle),
        "centers": _w(centers),
        "ang_freq": _w(ang_freq),
        "w_rbf": _w((lambda *s: torch.randn(*s, dtype=torch.bfloat16) * 0.2)(NR, De)),
        "w_sbf": _w((lambda *s: torch.randn(*s, dtype=torch.bfloat16) * 0.2)(NR * L, De)),
        "w_down": _w((lambda *s: torch.randn(*s, dtype=torch.bfloat16) * 0.2)(De, De)),
        "w_up": _w((lambda *s: torch.randn(*s, dtype=torch.bfloat16) * 0.2)(De, De)),
    }

def reference(m, idx_in, idx_out, dist, angle, centers, ang_freq, w_rbf, w_sbf, w_down, w_up):
    E, De = m.shape[0], m.shape[1]
    NR = centers.shape[0]
    L = ang_freq.shape[0]
    rbf = torch.exp(-10.0 * (dist[:, None] - centers[None, :]) ** 2)
    cbf = torch.cos(ang_freq[None, :] * angle[:, None])
    rbf_t = rbf[idx_out]
    sbf = torch.reshape(rbf_t[:, :, None] * cbf[:, None, :], (-1, NR * L))
    x = (m[idx_in] @ w_down) * (sbf @ w_sbf)
    agg = _segment_sum(x, idx_out, E)
    return m + (agg @ w_up) * (rbf @ w_rbf)
```

```cpp
#include <cuda_runtime.h>
#include <cuda_bf16.h>
#include <cuda.h>
#include <stdint.h>

namespace gem {

constexpr int GPB      = 76;
constexpr int RPB      = GPB * 16;
constexpr int NAW      = 19;
constexpr int GPW      = 4;
constexpr int DW       = 19;
constexpr int SW0      = 20;
constexpr int NSW      = 4;
constexpr int PW0      = SW0 + NSW;
constexpr int NPW      = 4;
constexpr int NH       = 10;
constexpr int HD       = 4;
constexpr int PD       = 3;
constexpr int SB       = 4;
constexpr int W0 = 330, W1 = 338;
constexpr int NWARP    = PW0 + NPW;
constexpr int NTHR     = NWARP * 32;
constexpr int NAT      = NAW * 32;
constexpr int NBT      = NTHR - 32;
constexpr int NST      = NSW * 32;
constexpr int NPT      = NPW * 32;
constexpr int MAXG     = 132;
constexpr int NC       = 3;
constexpr int NR       = 2 * NC;
constexpr int PCAP     = 87;
constexpr int CELLB    = 384;
constexpr int SECB     = 192;
constexpr int HALFG    = MAXG / 2;
constexpr int GCAP     = 80;
constexpr int GSTRIDE  = 84;
constexpr int LISTN    = GPB * GSTRIDE;
constexpr int SPCAP    = 32;
constexpr unsigned BINMAGIC = 3532046u;
constexpr int OVFCAP   = 1 << 22;

constexpr int PRIMB    = MAXG * CELLB;
constexpr int STAGEB   = HALFG * CELLB;
constexpr int LISTB    = LISTN * 6;
constexpr int SM_X     = 0;
constexpr int SM_Y     = SM_X + PRIMB;
constexpr int SM_L1    = SM_X;
constexpr int SM_L0    = SM_Y + PRIMB;
constexpr int SM_STAGE = (SM_L0 + LISTB + 127) & ~127;
constexpr int SM_SEC   = SM_STAGE + STAGEB;
constexpr int SM_SPILL = SM_SEC + MAXG * SECB;
constexpr int SM_PCNT  = SM_SPILL + NR * SPCAP * 8;
constexpr int SM_GCNT  = SM_PCNT + NC * MAXG * 4;
constexpr int SM_SCNT  = SM_GCNT + 2 * 80 * 4;
constexpr int SM_ZEND  = SM_SCNT + 32;
constexpr int SM_TRASH = SM_ZEND;
constexpr int SM_MBAR  = SM_TRASH + 128;
constexpr int SM_TOTAL = SM_MBAR + 96;
constexpr int MB_FULL  = SM_MBAR;
constexpr int MB_EMPTY = SM_MBAR + 16;
constexpr int MB_EPI   = SM_MBAR + 32;
constexpr int MB_SEC   = SM_MBAR + 40;
constexpr int MB_TILE  = SM_MBAR + 64;
constexpr int MB_LEFT0 = SM_MBAR + 88;
constexpr int SM_MROW  = SM_Y;
constexpr int SM_WGT   = SM_MROW + RPB * 32;
constexpr int SM_DIST  = SM_WGT + 13 * 128;
static_assert(SM_DIST + RPB * 2 <= SM_L0, "epilogue operands must fit");
static_assert(LISTB <= PRIMB, "aliases must fit");
static_assert(SM_ZEND % 16 == 0 && SM_PCNT % 16 == 0 && SM_GCNT % 16 == 0 && LISTN % 8 == 0 && SM_Y % 128 == 0 && SM_L0 % 16 == 0 && SM_STAGE % 16 == 0 && SM_SEC % 16 == 0, "alignment");
static_assert(GPW * GSTRIDE == 336, "list clearing");
static_assert(SM_TOTAL <= 195 * 1024, "keep 60 KB of L1");

struct Params {
    const __nv_bfloat16* m;
    const int* idx_in;
    const int* idx_out;
    const __nv_bfloat16* dist;
    const __nv_bfloat16* angle;
    const __nv_bfloat16* centers;
    const __nv_bfloat16* freq;
    const __nv_bfloat16* w_rbf;
    const __nv_bfloat16* w_sbf;
    const __nv_bfloat16* w_down;
    const __nv_bfloat16* w_up;
    __nv_bfloat16* out;
    int E, T, G;
    int ts[NC], t0[NC];
    unsigned zero;
    cudaTextureObject_t mtex;
};

__device__ __align__(128) unsigned char g_cells[(size_t)NC * MAXG * MAXG * CELLB];
__device__ __align__(128) unsigned char g_sec[(size_t)NC * MAXG * MAXG * SECB];
__device__ uint2 g_ovf[OVFCAP];
__device__ unsigned g_ready[NC * 32];
__device__ unsigned g_ovfcnt;
__device__ unsigned g_done;
__device__ float g_acc[MAXG * RPB * 16];
#define TL(i) do {} while (0)

__device__ __forceinline__ unsigned smem_u32(const void* p) { return (unsigned)__cvta_generic_to_shared(p); }
__device__ __forceinline__ void bar_sync(int id, int n) { asm volatile("bar.sync %0, %1;" ::"r"(id), "r"(n) : "memory"); }
__device__ __forceinline__ void bar_arrive(int id, int n) { asm volatile("bar.arrive %0, %1;" ::"r"(id), "r"(n) : "memory"); }
__device__ __forceinline__ void mbar_init(unsigned a, unsigned n) { asm volatile("mbarrier.init.shared.b64 [%0], %1;" ::"r"(a), "r"(n) : "memory"); }
__device__ __forceinline__ void mbar_arrive(unsigned a) { asm volatile("mbarrier.arrive.shared.b64 _, [%0];" ::"r"(a) : "memory"); }
__device__ __forceinline__ void mbar_wait(unsigned a, unsigned parity) {
    unsigned ok, spins = 0;
    while (true) {
        asm volatile("{ .reg .pred p; mbarrier.try_wait.parity.shared.b64 p, [%1], %2; selp.u32 %0, 1, 0, p; }" : "=r"(ok) : "r"(a), "r"(parity) : "memory");
        if (ok) break;
        __nanosleep(100);
        if (++spins > (1u << 24)) __trap();
    }
}
__device__ __forceinline__ unsigned lds_u32(unsigned a) { unsigned v; asm volatile("ld.shared.u32 %0, [%1];" : "=r"(v) : "r"(a) : "memory"); return v; }
__device__ __forceinline__ unsigned lds_u16(unsigned a) { unsigned short v; asm volatile("ld.shared.u16 %0, [%1];" : "=h"(v) : "r"(a) : "memory"); return v; }
__device__ __forceinline__ void sts_u32(unsigned a, unsigned v) { asm volatile("st.shared.u32 [%0], %1;" ::"r"(a), "r"(v) : "memory"); }
__device__ __forceinline__ unsigned atoms_inc(unsigned addr) {
    unsigned r; asm volatile("atom.shared.add.u32 %0, [%1], 1;" : "=r"(r) : "r"(addr) : "memory"); return r;
}
__device__ __forceinline__ uint2 lds_u64(unsigned a) {
    uint2 v; asm volatile("ld.shared.v2.u32 {%0,%1}, [%2];" : "=r"(v.x), "=r"(v.y) : "r"(a) : "memory"); return v;
}
__device__ __forceinline__ unsigned ldsr_u32(unsigned a) {
    unsigned v; asm volatile("ld.relaxed.cta.shared.u32 %0, [%1];" : "=r"(v) : "r"(a) : "memory"); return v;
}
__device__ __forceinline__ uint2 ldsr_u64(unsigned a) {
    uint2 v; asm volatile("ld.relaxed.cta.shared.v2.u32 {%0,%1}, [%2];" : "=r"(v.x), "=r"(v.y) : "r"(a) : "memory"); return v;
}
__device__ __forceinline__ unsigned eqmask2(unsigned a, unsigned b) {
    unsigned d; asm("set.eq.u32.f16x2 %0, %1, %2;" : "=r"(d) : "r"(a), "r"(b)); return d;
}
__device__ __forceinline__ void mma16816(float (&d)[4], unsigned a0, unsigned a1, unsigned a2, unsigned a3, unsigned b0, unsigned b1) {
    asm volatile("mma.sync.aligned.m16n8k16.row.col.f32.bf16.bf16.f32 {%0,%1,%2,%3}, {%4,%5,%6,%7}, {%8,%9}, {%0,%1,%2,%3};"
                 : "+f"(d[0]), "+f"(d[1]), "+f"(d[2]), "+f"(d[3]) : "r"(a0), "r"(a1), "r"(a2), "r"(a3), "r"(b0), "r"(b1));
}
__device__ __forceinline__ void mma1688(float (&d)[4], unsigned a0, unsigned a1, unsigned b0) {
    asm volatile("mma.sync.aligned.m16n8k8.row.col.f32.bf16.bf16.f32 {%0,%1,%2,%3}, {%4,%5}, {%6}, {%0,%1,%2,%3};"
                 : "+f"(d[0]), "+f"(d[1]), "+f"(d[2]), "+f"(d[3]) : "r"(a0), "r"(a1), "r"(b0));
}
__device__ __forceinline__ unsigned pack_bf16(float lo, float hi) {
    unsigned d; asm("cvt.rn.bf16x2.f32 %0, %1, %2;" : "=r"(d) : "f"(hi), "f"(lo)); return d;
}
__device__ __forceinline__ float bf_lo(unsigned u) { return __uint_as_float(u << 16); }
__device__ __forceinline__ float bf_hi(unsigned u) { return __uint_as_float(u & 0xffff0000u); }
__device__ __forceinline__ unsigned mul_bf16x2(unsigned a, unsigned b) {
    unsigned d; asm("mul.rn.bf16x2 %0, %1, %2;" : "=r"(d) : "r"(a), "r"(b)); return d;
}
__device__ __forceinline__ unsigned sub_bf16x2(unsigned a, unsigned b) {
    unsigned d; asm("sub.rn.bf16x2 %0, %1, %2;" : "=r"(d) : "r"(a), "r"(b)); return d;
}
__device__ __forceinline__ unsigned ldg_u32(const void* p) {
    unsigned v; asm volatile("ld.global.nc.u32 %0, [%1];" : "=r"(v) : "l"(p)); return v;
}

__constant__ unsigned c_inv2pi[8] = {0u, 0x28be60dbu, 0x9391054au, 0x7f09d5f4u, 0x7d4d3770u, 0x36d8a566u, 0x4f10e410u, 0x7f9458eau};
__device__ __forceinline__ float cos_wide(unsigned h) {
    unsigned e = (h >> 7) & 0xffu;
    if (e < 128u) return __cosf(__uint_as_float(h << 16));
    unsigned mant = (h & 0x7fu) | 0x80u, p = e - 102u;
    unsigned w0 = c_inv2pi[p >> 5], w1 = c_inv2pi[(p >> 5) + 1], w2 = c_inv2pi[(p >> 5) + 2];
    unsigned hi = __funnelshift_l(w1, w0, p), lo = __funnelshift_l(w2, w1, p);
    int turns = (int)(mant * hi + __umulhi(mant, lo));
    float c = __cosf((float)turns * 1.46291807926715968e-9f);
    return e == 255u ? __uint_as_float(0x7fc00000u) : c;
}
__device__ __forceinline__ unsigned cos2_fast(unsigned x) { return pack_bf16(__cosf(bf_lo(x)), __cosf(bf_hi(x))); }

__device__ __forceinline__ void push_overflow(unsigned x, unsigned c, unsigned bin) {
    unsigned k = atomicAdd(&g_ovfcnt, 1u);
    if (k < (unsigned)OVFCAP) g_ovf[k] = make_uint2(x, (c & 0xffffu) | (bin << 16));
}
__device__ __forceinline__ unsigned make_x(unsigned in, unsigned loc) {
    return (in << 2) | ((loc * 0x10010000u) & 0xf7f00000u);
}

struct Unit { int4 in, out; uint2 an; };

__device__ __forceinline__ void rank_unit(unsigned cnt, Unit& u, bool ok, unsigned trash, unsigned (&rank)[4]) {
    int* o[4] = {&u.out.x, &u.out.y, &u.out.z, &u.out.w};
#pragma unroll
    for (int i = 0; i < 4; i++) {
        unsigned bin = __umulhi((unsigned)*o[i], BINMAGIC);
        *o[i] += bin * (65536 - RPB);
        rank[i] = atoms_inc(ok ? cnt + bin * 4 : trash);
    }
}

__device__ __forceinline__ unsigned cos2_slow(unsigned x) { return pack_bf16(cos_wide(x & 0xffffu), cos_wide(x >> 16)); }
__device__ __forceinline__ void store_late(unsigned sbase, int tile, unsigned x, unsigned c, unsigned bin, unsigned rank) {
    if (rank >= PCAP) {
        push_overflow(x, c, bin);
    } else {
        if (tile > 0) mbar_wait(sbase + MB_SEC + (tile - 1) * 8, 0);
        asm volatile("st.shared.v2.u32 [%0], {%1,%2};" ::"r"(sbase + SM_SEC + bin * SECB + (rank - 63) * 8),
                     "r"(x), "r"(c) : "memory");
    }
}

__device__ __forceinline__ void store_unit(unsigned sbase, int tile, const Unit& u, const unsigned (&rank)[4], unsigned f2) {
    const unsigned cells = sbase + (tile ? SM_Y : SM_X);
    const unsigned o[4] = {(unsigned)u.out.x, (unsigned)u.out.y, (unsigned)u.out.z, (unsigned)u.out.w};
    const unsigned q[4] = {(unsigned)u.in.x, (unsigned)u.in.y, (unsigned)u.in.z, (unsigned)u.in.w};
    const unsigned x01 = mul_bf16x2(u.an.x, f2), x23 = mul_bf16x2(u.an.y, f2);
    unsigned c01 = cos2_fast(x01), c23 = cos2_fast(x23);
    const unsigned big = __vmaxu2(x01 & 0x7fff7fffu, x23 & 0x7fff7fffu);
    if ((big + 0x3dff3dffu) & 0x80008000u) {
        unsigned y01 = x01, y23 = x23;
#pragma unroll 1
        for (int i = 0; i < 4; i++) {
            unsigned c = pack_bf16(cos_wide(y01 & 0xffffu), 0.f);
            y01 = __funnelshift_r(y01, y23, 16); y23 >>= 16;
            c01 = __funnelshift_r(c01, c23, 16); c23 = (c23 >> 16) | (c << 16);
        }
    }
    const unsigned c[4] = {c01, c01 >> 16, c23, c23 >> 16};
    unsigned x[4];
#pragma unroll
    for (int i = 0; i < 4; i++) {
        unsigned bin2 = o[i] >> 15, cell = cells + bin2 * (CELLB / 2), pos = (rank[i] ^ bin2) & 63u;
        x[i] = make_x(q[i], o[i]);
        asm volatile("{ .reg .pred p; setp.lt.u32 p, %4, 63; @p st.shared.u32 [%0], %2; @p st.shared.u16 [%1 + 256], %3; }"
                     ::"r"(cell + pos * 4), "r"(cell + pos * 2), "r"(x[i]), "h"((unsigned short)c[i]), "r"(rank[i]) : "memory");
    }
    if (max(max((int)rank[0], (int)rank[1]), max((int)rank[2], (int)rank[3])) >= 63) {
#pragma unroll
        for (int i = 0; i < 4; i++)
            if (rank[i] >= 63) store_late(sbase, tile, x[i], c[i], o[i] >> 16, rank[i]);
    }
}

struct Tile { int u0, nun; };
__device__ __forceinline__ Tile tile_of(const Params& P, int c) {
    int t0 = P.t0[c] + blockIdx.x * P.ts[c];
    int t1 = min(t0 + P.ts[c], P.T & ~3);
    Tile t; t.u0 = t0 >> 2; t.nun = (t1 - t0) >> 2;
    return t;
}
__device__ __forceinline__ void load_unit(const Params& P, int u, Unit& v) {
    v.out = __ldcs(reinterpret_cast<const int4*>(P.idx_out) + u);
    v.in = __ldcs(reinterpret_cast<const int4*>(P.idx_in) + u);
    v.an = __ldcs(reinterpret_cast<const uint2*>(P.angle) + u);
}
__device__ __forceinline__ void load_unit_if(const Params& P, const Tile& t, int u, Unit& v) {
    if (u < t.nun) load_unit(P, t.u0 + u, v);
}
__device__ __forceinline__ void bin_step(unsigned sbase, int tile, Unit& v, const Tile& t, int u0, int lane, unsigned f2) {
    if (u0 < t.nun) {
        unsigned rank[4];
        rank_unit(sbase + SM_PCNT + tile * MAXG * 4, v, u0 + lane < t.nun, sbase + SM_TRASH + lane * 4, rank);
        store_unit(sbase, tile, v, rank, f2);
    }
}
__device__ __forceinline__ void bin_rest(const Params& P, unsigned sbase, int tile, const Tile& t, int first, int step, unsigned f2) {
#pragma unroll 1
    for (int u = first; u < t.nun; u += step) {
        Unit w; unsigned rank[4];
        load_unit(P, t.u0 + u, w);
        rank_unit(sbase + SM_PCNT + tile * MAXG * 4, w, true, 0u, rank);
        store_unit(sbase, tile, w, rank, f2);
    }
}

__device__ __forceinline__ void bulk_store(void* dst, unsigned src, unsigned bytes) {
    asm volatile("cp.async.bulk.global.shared::cta.bulk_group [%0], [%1], %2;" ::"l"(dst), "r"(src), "r"(bytes) : "memory");
}
__device__ __forceinline__ void bulk_load(unsigned dst, const void* src, unsigned bytes, unsigned mbar) {
    asm volatile("cp.async.bulk.shared::cluster.global.mbarrier::complete_tx::bytes [%0], [%1], %2, [%3];"
                 ::"r"(dst), "l"(src), "r"(bytes), "r"(mbar) : "memory");
}

__device__ __forceinline__ void flush_cells(const Params& P, const CUtensorMap* map, unsigned sbase, int c, int lane) {
    const unsigned cells = sbase + (c ? SM_Y : SM_X), cnt = sbase + SM_PCNT + c * MAXG * 4;
    unsigned more = 0;
#pragma unroll
    for (int k = 0; k < (MAXG + 31) / 32; k++) {
        const int bin = lane + 32 * k;
        if (bin < P.G) {
            const unsigned n = min(lds_u32(cnt + bin * 4), (unsigned)PCAP);
            asm volatile("st.shared.u16 [%0], %1;" ::"r"(cells + bin * CELLB + 256 + ((63 ^ (2 * bin)) & 63) * 2), "h"((unsigned short)n) : "memory");
            more |= (n > 63) << k;
        }
    }
    __syncwarp();
    asm volatile("fence.proxy.async.shared::cta;" ::: "memory");
    for (; more; more &= more - 1) {
        const int bin = lane + 32 * (__ffs(more) - 1);
        bulk_store(g_sec + ((size_t)(c * MAXG + bin) * MAXG + blockIdx.x) * SECB, sbase + SM_SEC + bin * SECB, SECB);
    }
    asm volatile("cp.async.bulk.commit_group;" ::: "memory");
    if (lane == 0)
        asm volatile("cp.async.bulk.tensor.3d.global.shared::cta.bulk_group [%0, {%1, %2, %3}], [%4];"
                     ::"l"(map), "r"(0), "r"((int)blockIdx.x), "r"(c * MAXG), "r"(cells) : "memory");
    asm volatile("cp.async.bulk.commit_group;" ::: "memory");
    __syncwarp();
}

__device__ __forceinline__ void spill_record(unsigned sbase, int r, unsigned x, unsigned c) {
    unsigned q = atoms_inc(sbase + SM_SCNT + r * 4);
    if (q < SPCAP) asm volatile("st.shared.v2.u32 [%0], {%1,%2};" ::"r"(sbase + SM_SPILL + (r * SPCAP + q) * 8), "r"(x), "r"(c & 0xffffu) : "memory");
}

template <int N>
__device__ __forceinline__ void sort_records(unsigned sbase, int r, unsigned trash,
                                             const unsigned (&x)[N], const unsigned (&c)[N], const bool (&ok)[N]) {
    unsigned rank[N], g4[N]; int worst = 0;
    const int buf = r & 1;
    const unsigned cnt = sbase + SM_GCNT + buf * 320, lst = sbase + (buf ? SM_L1 : SM_L0);
#pragma unroll
    for (int k = 0; k < N; k++) {
        g4[k] = (x[k] >> 18) & 0x1fcu;
        rank[k] = atoms_inc(cnt + (ok[k] ? g4[k] : trash - cnt));
    }
#pragma unroll
    for (int k = 0; k < N; k++) {
        unsigned e = g4[k] * (GSTRIDE / 4) + rank[k];
        asm volatile("{ .reg .pred p; setp.lt.u32 p, %4, %5; @p st.shared.u32 [%0], %2; @p st.shared.u16 [%1 + %6], %3; }"
                     ::"r"(lst + e * 4), "r"(lst + e * 2), "r"(x[k] & 0xf00fffffu), "h"((unsigned short)c[k]),
                       "r"(rank[k]), "n"(GCAP), "n"(LISTN * 4) : "memory");
        worst = max(worst, (int)rank[k]);
    }
    if (worst >= GCAP) {
#pragma unroll
        for (int k = 0; k < N; k++)
            if ((int)rank[k] >= GCAP) spill_record(sbase, r, x[k], c[k]);
    }
}

__device__ __forceinline__ int first_cell(const Params& P, int r) { return (r & 1) * ((P.G + 1) >> 1); }
__device__ __forceinline__ int num_cells(const Params& P, int r) { return min((P.G + 1) >> 1, P.G - first_cell(P, r)); }

__device__ __forceinline__ void stage_round(const Params& P, unsigned sbase, int r, int stid) {
    const int c = r >> 1, p0 = first_cell(P, r), np = num_cells(P, r);
    const unsigned char* src = g_cells + ((size_t)(c * MAXG + blockIdx.x) * MAXG + p0) * CELLB + stid * 16;
    const unsigned dst = sbase + SM_STAGE + stid * 16;
#pragma unroll
    for (int k = 0; k < (STAGEB / 16 + NST - 1) / NST; k++)
        if ((k * NST + stid) * 16 < np * CELLB)
            asm volatile("cp.async.cg.shared.global [%0], [%1], 16;" ::"r"(dst + k * NST * 16), "l"(src + k * NST * 16) : "memory");
    asm volatile("cp.async.commit_group;" ::: "memory");
}

__device__ __forceinline__ void sort_round(const Params& P, unsigned sbase, int r, int sw, int lane) {
    static_assert(HALFG == 66 && NSW == 4, "cell ownership");
    const int p0 = first_cell(P, r), np = num_cells(P, r);
    const unsigned trash = sbase + SM_TRASH + lane * 4, stage = sbase + SM_STAGE;
    const int cell = 32 * (sw & 1) + lane, xcell = 64 + (sw >> 1);
    const unsigned mine = stage + cell * CELLB, extra = stage + xcell * CELLB;
    unsigned n = 0, nx = 0;
    const int key = blockIdx.x & 31;
    if (cell < np) n = lds_u16(mine + 256 + (63 ^ (2 * key)) * 2);
    if (xcell < np) nx = lds_u16(extra + 256 + (63 ^ (2 * key)) * 2);
    const int lim = (int)min(n, 63u);
    const unsigned char* sec = g_sec + ((size_t)((r >> 1) * MAXG + blockIdx.x) * MAXG + p0) * SECB;
    unsigned more = __ballot_sync(0xffffffffu, n > 63) & (0x55555555u << (sw >> 1));
    unsigned x2[2] = {0u, 0u}, c2[2] = {0u, 0u}; bool ok2[2];
    const unsigned char* sec0 = sec + (32 * (sw & 1) + __ffs(more) - 1) * SECB;
    ok2[0] = more && 63 + lane < __shfl_sync(0xffffffffu, n, (__ffs(more) - 1) & 31);
    if (ok2[0]) { uint2 v = __ldcg(reinterpret_cast<const uint2*>(sec0) + lane); x2[0] = v.x; c2[0] = v.y; }
    more &= more - 1;
    const int first = ((sw >> 1) * 16) ^ lane ^ (r & P.zero);
#pragma unroll
    for (int s = 0; s < 16; s += SB) {
        unsigned x[2 * SB], c[2 * SB]; bool ok[2 * SB];
#pragma unroll
        for (int k = 0; k < SB; k++) {
            int pair = (s + k) ^ first;
            uint2 xx = lds_u64(mine + (pair ^ key) * 8);
            unsigned cc = lds_u32(mine + 256 + (pair ^ key) * 4);
            x[2 * k] = xx.x; x[2 * k + 1] = xx.y; c[2 * k] = cc; c[2 * k + 1] = cc >> 16;
            ok[2 * k] = 2 * pair < lim; ok[2 * k + 1] = 2 * pair + 1 < lim;
        }
        sort_records<2 * SB>(sbase, r, trash, x, c, ok);
    }
    {
        int slot = (sw & 1) * 32 + lane;
        x2[1] = lds_u32(extra + (slot ^ (2 * key)) * 4);
        c2[1] = lds_u16(extra + 256 + (slot ^ (2 * key)) * 2);
        ok2[1] = slot < (int)min(nx, 63u);
        sort_records<2>(sbase, r, trash, x2, c2, ok2);
    }
    bool xmore = (sw & 1) && nx > 63;
    while (more || xmore) {
        int k = more ? __ffs(more) - 1 : 0;
        unsigned nk = __shfl_sync(0xffffffffu, n, k);
        int ck = 32 * (sw & 1) + k;
        if (!more) { nk = nx; ck = xcell; xmore = false; }
        more &= more - 1;
        unsigned x[1] = {0u}, c[1] = {0u}; bool ok[1];
        ok[0] = 63 + lane < nk;
        if (ok[0]) { uint2 v = __ldcg(reinterpret_cast<const uint2*>(sec + ck * SECB) + lane); x[0] = v.x; c[0] = v.y; }
        sort_records<1>(sbase, r, trash, x, c, ok);
    }
}

__device__ __forceinline__ uint2 gather(cudaTextureObject_t tex, unsigned e, unsigned t) {
    uint2 v;
    asm volatile("{ .reg .u32 i, z, w; lop3.b32 i, %3, 0x0fffffff, %4, 0xea; tex.1d.v4.u32.s32 {%0,%1,z,w}, [%2, {i}]; }"
                 : "=r"(v.x), "=r"(v.y) : "l"(tex), "r"(e), "r"(t) : "memory");
    return v;
}
__device__ __forceinline__ unsigned transpose8(unsigned a) {
    unsigned d; asm volatile("movmatrix.sync.aligned.m8n8.trans.b16 %0, %1;" : "=r"(d) : "r"(a)); return d;
}

__device__ __forceinline__ void clear_lists(unsigned lst, int e0, int n, unsigned unused, int tid, int nthr) {
    for (int i = tid; i < n / 4; i += nthr)
        asm volatile("st.shared.v4.u32 [%0], {%1,%1,%1,%1};" ::"r"(lst + e0 * 4 + i * 16), "r"(unused) : "memory");
    for (int i = tid; i < n / 8; i += nthr)
        asm volatile("st.shared.v4.u32 [%0], {%1,%1,%1,%1};" ::"r"(lst + LISTN * 4 + e0 * 2 + i * 16), "r"(0u) : "memory");
}

__device__ __forceinline__ void brute_list(const unsigned char* xs, int xstep, const unsigned char* cs, int cstep, unsigned kx, unsigned n, int tag,
                                           const uint2* m, unsigned lg0, int lane, float (&acc)[GPW][2][4]) {
    const int t = lane & 3;
    const unsigned glo = (lane >> 2) * 0x10001u, ghi = glo + 0x80008u, half = (lane & 4) ? 0x7632u : 0x5410u;
#pragma unroll 1
    for (unsigned base = 0; base < n; base += 16) {
        unsigned y[4], row[4]; uint2 v[4]; bool any = false;
#pragma unroll
        for (int i = 0; i < 4; i++) {
            unsigned k = base + 4 * t + i, x = 0; unsigned short c = 0, b = 0;
            if (k < n) {
                asm volatile("ld.volatile.u32 %0, [%1];" : "=r"(x) : "l"(xs + (size_t)(k ^ kx) * xstep) : "memory");
                asm volatile("ld.volatile.u16 %0, [%1];" : "=h"(c) : "l"(cs + (size_t)(k ^ kx) * cstep) : "memory");
                if (tag >= 0) asm volatile("ld.volatile.u16 %0, [%1];" : "=h"(b) : "l"(cs + (size_t)(k ^ kx) * cstep + 2) : "memory");
            }
            const unsigned grp = (x >> 20) & 127u;
            bool mine = k < n && (tag < 0 || (int)b == tag) && grp - lg0 < (unsigned)GPW;
            v[i] = make_uint2(0u, 0u);
            if (mine) v[i] = __ldg(m + (x & 0xfffffu) + (lane >> 3));
            y[i] = mine ? c | (grp << 16) : 0xffff0000u;
            row[i] = x >> 28;
            any |= mine;
        }
        if (!__any_sync(0xffffffffu, any)) continue;
        unsigned r01 = row[0] | (row[1] << 16), r23 = row[2] | (row[3] << 16);
        unsigned e0 = __byte_perm(v[0].x, v[1].x, half), e1 = __byte_perm(v[2].x, v[3].x, half);
        unsigned o0 = __byte_perm(v[0].y, v[1].y, half), o1 = __byte_perm(v[2].y, v[3].y, half);
#pragma unroll
        for (int j = 0; j < GPW; j++) {
            unsigned cj[4];
#pragma unroll
            for (int i = 0; i < 4; i++) cj[i] = (y[i] >> 16) == lg0 + j ? (y[i] & 0xffffu) : 0u;
            unsigned c01 = cj[0] | (cj[1] << 16), c23 = cj[2] | (cj[3] << 16);
            unsigned a0 = c01 & eqmask2(r01, glo), a1 = c01 & eqmask2(r01, ghi);
            unsigned a2 = c23 & eqmask2(r23, glo), a3 = c23 & eqmask2(r23, ghi);
            mma16816(acc[j][0], a0, a1, a2, a3, e0, e1);
            mma16816(acc[j][1], a0, a1, a2, a3, o0, o1);
        }
    }
}

__device__ __forceinline__ unsigned ld_pair(const __nv_bfloat16* w, int i0, int i1) {
    unsigned lo = __ldg(reinterpret_cast<const unsigned short*>(w) + i0);
    unsigned hi = __ldg(reinterpret_cast<const unsigned short*>(w) + i1);
    return lo | (hi << 16);
}

__device__ __forceinline__ float exp_fast(float x) {
    float y; asm("ex2.approx.ftz.f32 %0, %1;" : "=f"(y) : "f"(x * 1.44269504088896341f)); return y;
}
__device__ __forceinline__ unsigned rbf_pair(unsigned d2, unsigned cen2) {
    unsigned df = sub_bf16x2(d2, cen2);
    unsigned sq = mul_bf16x2(df, df);
    unsigned ar = mul_bf16x2(sq, 0xc120c120u);
    return pack_bf16(exp_fast(bf_lo(ar)), exp_fast(bf_hi(ar)));
}

struct EpiW { unsigned wd[2][2], wu[2][2], ws[2], wr[2], cen; };

__device__ __forceinline__ void load_epi_weights(const Params& P, int g, int t, EpiW& W) {
#pragma unroll
    for (int j = 0; j < 2; j++) {
        int mid = 8 * j + g;
        int oc = 4 * (g >> 1) + 2 * j + (g & 1);
        W.wd[j][0] = ld_pair(P.w_down, (4 * t) * 16 + mid, (4 * t + 1) * 16 + mid);
        W.wd[j][1] = ld_pair(P.w_down, (4 * t + 2) * 16 + mid, (4 * t + 3) * 16 + mid);
        W.wu[j][0] = ld_pair(P.w_up, (2 * t) * 16 + oc, (2 * t + 1) * 16 + oc);
        W.wu[j][1] = ld_pair(P.w_up, (2 * t + 8) * 16 + oc, (2 * t + 9) * 16 + oc);
        W.ws[j] = ld_pair(P.w_sbf, (2 * t) * 16 + mid, (2 * t + 1) * 16 + mid);
        W.wr[j] = ld_pair(P.w_rbf, (2 * t) * 16 + oc, (2 * t + 1) * 16 + oc);
    }
    W.cen = ld_pair(P.centers, 2 * t, 2 * t + 1);
}

__device__ __forceinline__ void epilogue_group(const EpiW& W, unsigned r0, unsigned r1, uint2& ma, uint2& mb,
                                               unsigned a0, unsigned a1, unsigned a2, unsigned a3) {
    float y[2][4], s[2][4], z[2][4], r[2][4];
#pragma unroll
    for (int j = 0; j < 2; j++) {
#pragma unroll
        for (int i = 0; i < 4; i++) { y[j][i] = 0.f; s[j][i] = 0.f; z[j][i] = 0.f; r[j][i] = 0.f; }
        mma16816(y[j], a0, a1, a2, a3, W.wd[j][0], W.wd[j][1]);
        mma1688(s[j], r0, r1, W.ws[j]);
        mma1688(r[j], r0, r1, W.wr[j]);
    }
    unsigned q0 = pack_bf16(y[0][0] * s[0][0], y[0][1] * s[0][1]);
    unsigned q1 = pack_bf16(y[0][2] * s[0][2], y[0][3] * s[0][3]);
    unsigned q2 = pack_bf16(y[1][0] * s[1][0], y[1][1] * s[1][1]);
    unsigned q3 = pack_bf16(y[1][2] * s[1][2], y[1][3] * s[1][3]);
    mma16816(z[0], q0, q1, q2, q3, W.wu[0][0], W.wu[0][1]);
    mma16816(z[1], q0, q1, q2, q3, W.wu[1][0], W.wu[1][1]);
    ma.x = pack_bf16(fmaf(z[0][0], r[0][0], bf_lo(ma.x)), fmaf(z[0][1], r[0][1], bf_hi(ma.x)));
    ma.y = pack_bf16(fmaf(z[1][0], r[1][0], bf_lo(ma.y)), fmaf(z[1][1], r[1][1], bf_hi(ma.y)));
    mb.x = pack_bf16(fmaf(z[0][2], r[0][2], bf_lo(mb.x)), fmaf(z[0][3], r[0][3], bf_hi(mb.x)));
    mb.y = pack_bf16(fmaf(z[1][2], r[1][2], bf_lo(mb.y)), fmaf(z[1][3], r[1][3], bf_hi(mb.y)));
}

__device__ __forceinline__ void epilogue_smem(const EpiW& W, unsigned sbase, int aw, int j, int lane, const uint2* dst, int left, const float (&acc)[2][4]) {
    const int g = lane >> 2;
    const unsigned r0 = rbf_pair(lds_u16(sbase + SM_DIST + ((aw * GPW + j) * 16 + g) * 2) * 0x10001u, W.cen);
    const unsigned r1 = rbf_pair(lds_u16(sbase + SM_DIST + ((aw * GPW + j) * 16 + g + 8) * 2) * 0x10001u, W.cen);
    uint2 ma = lds_u64(sbase + SM_MROW + (aw * GPW + j) * 512 + lane * 8);
    uint2 mb = lds_u64(sbase + SM_MROW + (aw * GPW + j) * 512 + 256 + lane * 8);
    epilogue_group(W, r0, r1, ma, mb, pack_bf16(acc[0][0], acc[0][1]), pack_bf16(acc[0][2], acc[0][3]),
                   pack_bf16(acc[1][0], acc[1][1]), pack_bf16(acc[1][2], acc[1][3]));
    asm volatile("{ .reg .pred p, q; setp.gt.s32 p, %5, 0; setp.gt.s32 q, %5, 8;\n"
                 "@p st.global.v2.u32 [%0], {%1,%2}; @q st.global.v2.u32 [%0 + 256], {%3,%4}; }"
                 ::"l"(dst + j * 64), "r"(ma.x), "r"(ma.y), "r"(mb.x), "r"(mb.y), "r"(left - j * 16) : "memory");
}

__device__ __forceinline__ void wait_flag(const unsigned* flag, unsigned target) {
    unsigned v, spins = 0;
    do {
        asm volatile("ld.acquire.gpu.global.u32 %0, [%1];" : "=r"(v) : "l"(flag) : "memory");
        if (++spins > (1u << 24)) __trap();
    } while (v < target);
}

__global__ void __launch_bounds__(NTHR, 1) fused_kernel(const __grid_constant__ Params P, const __grid_constant__ CUtensorMap map) {
    extern __shared__ __align__(128) unsigned char smem[];
    const unsigned sbase = smem_u32(smem);
    const int tid = threadIdx.x, warp = __shfl_sync(0xffffffffu, tid >> 5, 0), lane = tid & 31;
    if (warp == 0) TL(0);
    const unsigned unused = blockIdx.x * (RPB * 4);

    if (warp == DW) {
        for (int i = lane; i < (SM_ZEND - SM_PCNT) / 16; i += 32)
            reinterpret_cast<uint4*>(smem + SM_PCNT)[i] = make_uint4(0u, 0u, 0u, 0u);
        sts_u32(sbase + SM_TRASH + lane * 4, 0x80000000u);
        if (lane < 12) mbar_init(sbase + SM_MBAR + lane * 8, lane < 2 ? NSW : (lane < 4 ? NAT : 1));
        __syncwarp();
        bar_sync(0, NTHR);
#pragma unroll 1
        for (int c = 0; c < NC; c++) {
            bar_sync(4 + c, c == 0 ? NTHR : (c == 1 ? NPT + NH * 32 + 32 : NPT + 32));
            flush_cells(P, &map, sbase, c, lane);
            asm volatile("cp.async.bulk.wait_group.read 1;" ::: "memory");
            __syncwarp();
            if (lane == 0) mbar_arrive(sbase + MB_SEC + c * 8);
            asm volatile("cp.async.bulk.wait_group.read 0;" ::: "memory");
            __syncwarp();
            if (c == 0 && lane == 0) mbar_arrive(sbase + MB_LEFT0);
            if (c == 1) bar_arrive(7, NPT + 32);
            asm volatile("cp.async.bulk.wait_group 0;" ::: "memory");
            __syncwarp();
            TL(60 + c);
            if (lane == 0) {
                asm volatile("red.release.gpu.global.add.u32 [%0], 1;" ::"l"(&g_ready[c * 32]) : "memory");
                if (c == 1) { wait_flag(&g_ready[c * 32], P.G); mbar_arrive(sbase + MB_TILE + c * 8); }
            }
            __syncwarp();
            TL(44 + c);
        }
        const int rows = min(RPB, P.E - (int)blockIdx.x * RPB);
        if (lane == 0) {
            const unsigned db = (rows * 2) & ~15u;
            asm volatile("mbarrier.expect_tx.relaxed.cta.shared::cta.b64 [%0], %1;" ::"r"(sbase + MB_EPI), "r"(rows * 32 + db) : "memory");
            bulk_load(sbase + SM_MROW, P.m + (size_t)blockIdx.x * RPB * 16, rows * 32, sbase + MB_EPI);
            if (db) bulk_load(sbase + SM_DIST, P.dist + (size_t)blockIdx.x * RPB, db, sbase + MB_EPI);
        }
        __syncwarp();
        EpiW W;
        load_epi_weights(P, lane >> 2, lane & 3, W);
        const int i = (rows & ~7) + lane;
        if (i < rows) {
            unsigned short d = __ldg(reinterpret_cast<const unsigned short*>(P.dist) + blockIdx.x * RPB + i);
            asm volatile("st.shared.u16 [%0], %1;" ::"r"(sbase + SM_DIST + i * 2), "h"(d) : "memory");
        }
        const unsigned* wp = reinterpret_cast<const unsigned*>(&W);
#pragma unroll
        for (int k = 0; k < 13; k++) sts_u32(sbase + SM_WGT + k * 128 + lane * 4, wp[k]);
        __syncwarp();
        if (lane == 0) {
            wait_flag(&g_ready[64], P.G);
            sts_u32(sbase + SM_SCNT + NR * 4, min(__ldcg(&g_ovfcnt), (unsigned)OVFCAP));
            mbar_arrive(sbase + MB_TILE + 16);
            mbar_arrive(sbase + MB_EPI);
        }
        __syncwarp();
        bar_sync(3, NAT + 32);
        if (lane == 0) {
            if (atomicInc(&g_done, gridDim.x - 1) == gridDim.x - 1) {
                g_ready[0] = 0; g_ready[32] = 0; g_ready[64] = 0;
                g_ovfcnt = 0;
            }
        }
        return;
    }

    {
        const int btid = tid - (warp > DW ? 32 : 0);
        const unsigned f2 = (unsigned)__ldg(reinterpret_cast<const unsigned short*>(P.freq)) * 0x10001u;
        Unit a[2];
        const Tile cur = tile_of(P, 0);
#pragma unroll
        for (int k = 0; k < 2; k++) {
            a[k].in = make_int4(0, 0, 0, 0); a[k].out = a[k].in; a[k].an = make_uint2(0u, 0u);
            load_unit_if(P, cur, btid + k * NBT, a[k]);
        }
        clear_lists(sbase + SM_L0, 0, LISTN, unused, btid, NBT);
        bar_sync(0, NTHR);
#pragma unroll
        for (int k = 0; k < 2; k++) bin_step(sbase, 0, a[k], cur, (warp - (warp > DW)) * 32 + k * NBT, lane, f2);
        bin_rest(P, sbase, 0, cur, btid + 2 * NBT, NBT, f2);
        if (blockIdx.x == 0 && tid < (P.T & 3)) {
            int k = (P.T & ~3) + tid;
            unsigned x = mul_bf16x2((unsigned)__ldg(reinterpret_cast<const unsigned short*>(P.angle) + k), f2);
            unsigned o = (unsigned)P.idx_out[k], bin = __umulhi(o, BINMAGIC);
            push_overflow(make_x(P.idx_in[k], o - bin * RPB), cos2_slow(x), bin);
        }
        bar_arrive(4, NTHR);
        if (warp == 0) TL(52);
        if (warp < NH) {
            const Tile t1 = tile_of(P, 1);
            constexpr int nthr = NPT + NH * 32;
            Unit b[HD];
#pragma unroll
            for (int k = 0; k < HD; k++) {
                b[k].in = make_int4(0, 0, 0, 0); b[k].out = b[k].in; b[k].an = make_uint2(0u, 0u);
                load_unit_if(P, t1, NPT + tid + k * nthr, b[k]);
            }
#pragma unroll
            for (int k = 0; k < HD; k++) bin_step(sbase, 1, b[k], t1, NPT + warp * 32 + k * nthr, lane, f2);
            bin_rest(P, sbase, 1, t1, NPT + tid + HD * nthr, nthr, f2);
            bar_arrive(5, nthr + 32);
        }
    }

    if (warp >= PW0) {
        const unsigned f2 = (unsigned)__ldg(reinterpret_cast<const unsigned short*>(P.freq)) * 0x10001u;
        Unit a[PD];
#pragma unroll 1
        for (int c = 1; c < NC; c++) {
            const Tile cur = tile_of(P, c);
            const int nthr = c == 1 ? NPT + NH * 32 : NPT, u0 = (warp - PW0) * 32;
#pragma unroll
            for (int k = 0; k < PD; k++) {
                a[k].in = make_int4(0, 0, 0, 0); a[k].out = a[k].in; a[k].an = make_uint2(0u, 0u);
                load_unit_if(P, cur, u0 + lane + k * nthr, a[k]);
            }
            if (c == 2) bar_sync(7, NPT + 32);
#pragma unroll 1
            for (int u = u0; u < cur.nun; u += PD * nthr) {
                unsigned rank[PD][4];
#pragma unroll
                for (int k = 0; k < PD; k++)
                    rank_unit(sbase + SM_PCNT + c * MAXG * 4, a[k], u + lane + k * nthr < cur.nun, sbase + SM_TRASH + lane * 4, rank[k]);
#pragma unroll
                for (int k = 0; k < PD; k++) {
                    store_unit(sbase, c, a[k], rank[k], f2);
                    load_unit_if(P, cur, u + lane + (k + PD) * nthr, a[k]);
                }
            }
            bar_arrive(4 + c, nthr + 32);
            if (warp == PW0) TL(52 + 3 * c);
        }
        return;
    }

    if (warp < SW0) {
        const int aw = warp;
        const int g = lane >> 2, t = lane & 3;
        const unsigned glo = g * 0x100010u, ghi = glo + 0x800080u;
        float acc[GPW][2][4];
#pragma unroll
        for (int j = 0; j < GPW; j++)
#pragma unroll
            for (int h = 0; h < 2; h++)
#pragma unroll
                for (int i = 0; i < 4; i++) acc[j][h][i] = 0.f;

        {
            uint2 v[GPW][2]; unsigned rr[GPW][2];
#define GEM_FETCH(j, ADDR)                                                                                         \
            {                                                                                                      \
                unsigned w0 = ldsr_u32(ADDR + (j) * GSTRIDE * 4), w1 = ldsr_u32(ADDR + (j) * GSTRIDE * 4 + 8);     \
                v[j][0] = gather(P.mtex, w0, t);                                                                   \
                v[j][1] = gather(P.mtex, w1, t);                                                                   \
                rr[j][0] = transpose8(__byte_perm(w0, 0u, 0x4343));                                                \
                rr[j][1] = transpose8(__byte_perm(w1, 0u, 0x4343));                                                \
            }
#define GEM_REDUCE(j)                                                                                              \
            {                                                                                                      \
                uint2 cs = ldsr_u64(ec + j * GSTRIDE * 2);                                                         \
                unsigned a0 = cs.x & eqmask2(rr[j][0], glo), a1 = cs.x & eqmask2(rr[j][0], ghi);                   \
                unsigned a2 = cs.y & eqmask2(rr[j][1], glo), a3 = cs.y & eqmask2(rr[j][1], ghi);                   \
                mma16816(acc[j][0], a0, a1, a2, a3, transpose8(v[j][0].x), transpose8(v[j][1].x));                 \
                mma16816(acc[j][1], a0, a1, a2, a3, transpose8(v[j][0].y), transpose8(v[j][1].y));                 \
            }
#define GEM_STEP(NEXT)                                                                                             \
            {                                                                                                      \
                GEM_FETCH(2, ea) GEM_FETCH(3, ea)                                                                  \
                GEM_REDUCE(0) GEM_REDUCE(1)                                                                        \
                             \
                ea = NEXT;                                                                                         \
                ea |= (__float_as_uint(acc[0][0][0]) | __float_as_uint(acc[0][1][0])) & P.zero;                    \
                ea |= (__float_as_uint(acc[1][0][0]) | __float_as_uint(acc[1][1][0])) & P.zero;                    \
                GEM_FETCH(0, ea) GEM_FETCH(1, ea)                                                                  \
                GEM_REDUCE(2) GEM_REDUCE(3)                                                                        \
            }
            mbar_wait(sbase + MB_LEFT0, 0);
            clear_lists(sbase + SM_L1, warp * GPW * GSTRIDE, GPW * GSTRIDE, unused, lane, 32);
            mbar_arrive(sbase + MB_EMPTY + 8);
            const unsigned own = sbase + aw * GPW * GSTRIDE * 4, ownc = (own + sbase) / 2 + LISTN * 4;
            unsigned ea, ec, rare = 0; int todo;
#define GEM_OPEN(R, EA, EC)                                                                                        \
            {                                                                                                      \
                EA = own + (((R) & 1) ? SM_L1 : SM_L0) + GCAP * 4; EC = ownc + (((R) & 1) ? SM_L1 : SM_L0) + GCAP * 2; \
                todo = 0;                                                                                          \
                if ((R) < NR) {                                                                                    \
                    mbar_wait(sbase + MB_FULL + ((R) & 1) * 8, ((R) >> 1) & 1);                                    \
                    const unsigned ln = lane | ((R) & P.zero);           \
                    const unsigned n = lds_u32(sbase + SM_GCNT + ((R) & 1) * 320 + aw * 16 + (ln & 3) * 4);        \
                    if (__reduce_max_sync(0xffffffffu, lds_u32(sbase + SM_SCNT + (R) * 4)) <= SPCAP) {             \
                        todo = (int)min(__reduce_max_sync(0xffffffffu, n), (unsigned)GCAP);                        \
                        EA += (ln >> 3) * 16 + (ln & 4) - GCAP * 4;                                                \
                        EC += (ln & 3) * 8 - GCAP * 2;                                                             \
                    }                                                                                              \
                }                                                                                                  \
            }
            GEM_OPEN(0, ea, ec)
            if (warp == 0) TL(33);
            GEM_FETCH(0, ea) GEM_FETCH(1, ea)
#pragma unroll 1
            for (int r = 0; r < NR; r++) {
#pragma unroll 1
                for (; todo > 16; todo -= 16, ec += 32) GEM_STEP(ea + 64)
                if (warp == 0 && r == 0) TL(34);
                if (r == NR - 1) {
                    mbar_wait(sbase + MB_EPI, 0);
                    rare = __reduce_max_sync(0xffffffffu, lds_u32(sbase + SM_SCNT + (lane & 7) * 4));
                    if (!rare) break;
                }
                const unsigned cur = (r & 1) ? SM_L1 : SM_L0;
                unsigned nx, nc;
                GEM_OPEN(r + 1, nx, nc)
                GEM_STEP(nx)
                ec = nc;
                const unsigned ln = lane | (r & P.zero);
                const unsigned back = r + 2 < NR, wa = own + cur + ln * 16, ca = ownc + cur + ln * 16;
                asm volatile("{ .reg .pred p, q, u, w;\n"
                             "setp.ne.u32 p, %5, 0; setp.lt.and.u32 q, %6, 20, p; setp.lt.and.u32 u, %6, 10, p; setp.lt.and.u32 w, %6, 4, p;\n"
                             "@p st.shared.v4.u32 [%0], {%3,%3,%3,%3}; @p st.shared.v4.u32 [%0 + 512], {%3,%3,%3,%3}; @q st.shared.v4.u32 [%0 + 1024], {%3,%3,%3,%3};\n"
                             "@p st.shared.v4.u32 [%1], {%4,%4,%4,%4}; @u st.shared.v4.u32 [%1 + 512], {%4,%4,%4,%4}; @w st.shared.u32 [%2], %4; }"
                             ::"r"(wa), "r"(ca), "r"(sbase + SM_GCNT + (r & 1) * 320 + aw * 16 + ln * 4), "r"(unused), "r"(0u), "r"(back), "r"(ln) : "memory");
                asm volatile("{ .reg .pred p; setp.ne.u32 p, %1, 0; @p mbarrier.arrive.shared.b64 _, [%0]; }"
                             ::"r"(sbase + MB_EMPTY + (r & 1) * 8), "r"(back) : "memory");
                if (warp == 0) TL(11 + r * 4);
            }
            if (rare) {
#pragma unroll 1
                for (int r = 0; r <= NR; r++) {
                    const unsigned ns = lds_u32(sbase + SM_SCNT + r * 4);
                    const int p0 = first_cell(P, r), nl = r < NR && ns > SPCAP ? 2 * num_cells(P, r) : 1;
#pragma unroll 1
                    for (int k = 0; k < nl; k++) {
                        const unsigned char* xs = r < NR ? smem + SM_SPILL + r * SPCAP * 8 : reinterpret_cast<const unsigned char*>(g_ovf);
                        const unsigned char* cs = xs + 4;
                        int xstep = 8, cstep = 8; unsigned cn = ns, kx = 0;
                        if (r < NR && ns > SPCAP) {
                            size_t cell = (size_t)((r >> 1) * MAXG + blockIdx.x) * MAXG + p0 + (k >> 1);
                            kx = (2 * blockIdx.x) & 63;
                            cn = __ldcg(reinterpret_cast<const unsigned short*>(g_cells + cell * CELLB + 256) + (63 ^ kx));
                            if (k & 1) {
                                xs = g_sec + cell * SECB; cs = xs + 4;
                                cn = max(cn, 63u) - 63u; kx = 0;
                            } else {
                                xs = g_cells + cell * CELLB; cs = xs + 256;
                                cn = min(cn, 63u); xstep = 4; cstep = 2;
                            }
                        }
                        brute_list(xs, xstep, cs, cstep, kx, cn, r < NR ? -1 : (int)blockIdx.x, reinterpret_cast<const uint2*>(P.m), aw * GPW, lane, acc);
                    }
                }
#pragma unroll
                for (int i = 0; i < 2; i++) { v[0][i] = make_uint2(0u, 0u); v[1][i] = v[0][i]; rr[0][i] = 0u; rr[1][i] = 0u; }
            }
            bar_arrive(3, NAT + 32);
            if (warp == 0) TL(31);
            GEM_FETCH(2, ea) GEM_FETCH(3, ea)
            EpiW W;
            unsigned* wp = reinterpret_cast<unsigned*>(&W);
#pragma unroll
            for (int i = 0; i < 13; i++) wp[i] = lds_u32(sbase + SM_WGT + i * 128 + lane * 4);
            const int row0 = (blockIdx.x * GPB + aw * GPW) * 16, left = P.E - row0 - g;
            const uint2* dst = reinterpret_cast<const uint2*>(P.out + (size_t)row0 * 16) + lane;
            GEM_REDUCE(0) GEM_REDUCE(1)
            epilogue_smem(W, sbase, aw, 0, lane, dst, left, acc[0]);
            epilogue_smem(W, sbase, aw, 1, lane, dst, left, acc[1]);
            GEM_REDUCE(2) GEM_REDUCE(3)
            epilogue_smem(W, sbase, aw, 2, lane, dst, left, acc[2]);
            epilogue_smem(W, sbase, aw, 3, lane, dst, left, acc[3]);
#undef GEM_STEP
#undef GEM_OPEN
#undef GEM_FETCH
#undef GEM_REDUCE
        }
        if (warp == 0) TL(3);
        return;
    }

    const int sw = warp - SW0, stid = tid - SW0 * 32;
    if (sw == 0) {
        wait_flag(&g_ready[0], P.G);
        if (lane == 0) mbar_arrive(sbase + MB_TILE);
    }
#pragma unroll 1
    for (int r = 0; r < NR; r++) {
        mbar_wait(sbase + MB_TILE + (r >> 1) * 8, 0);
        if (r) bar_sync(1, NST);
        stage_round(P, sbase, r, stid);
        if (r >= 1) mbar_wait(sbase + MB_EMPTY + (r & 1) * 8, ((r - 1) >> 1) & 1);
        if (sw == 0) TL(8 + r * 4);
        asm volatile("cp.async.wait_all;" ::: "memory");
        bar_sync(1, NST);
        if (sw == 0) TL(9 + r * 4);
        sort_round(P, sbase, r, sw, lane);
        __syncwarp();
        if (lane == 0) mbar_arrive(sbase + MB_FULL + (r & 1) * 8);
        if (sw == 0) TL(10 + r * 4);
    }
}

__global__ void fb_zero(int n) {
    for (int i = blockIdx.x * blockDim.x + threadIdx.x; i < n; i += gridDim.x * blockDim.x) g_acc[i] = 0.f;
}
__global__ void fb_scatter(const __grid_constant__ Params P) {
    const unsigned f2 = (unsigned)__ldg(reinterpret_cast<const unsigned short*>(P.freq)) * 0x10001u;
    for (long long i = blockIdx.x * (long long)blockDim.x + threadIdx.x; i < (long long)P.T * 8; i += (long long)gridDim.x * blockDim.x) {
        int k = (int)(i >> 3), g = (int)(i & 7);
        float c = bf_lo(cos2_slow(mul_bf16x2((unsigned)__ldg(reinterpret_cast<const unsigned short*>(P.angle) + k), f2)));
        unsigned v = ldg_u32(reinterpret_cast<const char*>(P.m) + (size_t)P.idx_in[k] * 32 + 4 * g);
        float* a = g_acc + (size_t)P.idx_out[k] * 16 + 2 * g;
        atomicAdd(a, c * bf_lo(v));
        atomicAdd(a + 1, c * bf_hi(v));
    }
}
__global__ void fb_epilogue(const __grid_constant__ Params P) {
    int lane = threadIdx.x & 31, g = lane >> 2, t = lane & 3;
    int grp = (blockIdx.x * blockDim.x + threadIdx.x) >> 5;
    if (grp * 16 >= P.E) return;
    EpiW W;
    load_epi_weights(P, g, t, W);
    float4 lo = *reinterpret_cast<const float4*>(g_acc + (size_t)(grp * 16 + g) * 16 + 4 * t);
    float4 hi = *reinterpret_cast<const float4*>(g_acc + (size_t)(grp * 16 + g + 8) * 16 + 4 * t);
    int ra = grp * 16 + g, rb = ra + 8;
    unsigned da = 0, db = 0; uint2 ma = make_uint2(0u, 0u), mb = ma;
    if (ra < P.E) { da = __ldg(reinterpret_cast<const unsigned short*>(P.dist) + ra); ma = __ldg(reinterpret_cast<const uint2*>(P.m + (size_t)ra * 16) + t); }
    if (rb < P.E) { db = __ldg(reinterpret_cast<const unsigned short*>(P.dist) + rb); mb = __ldg(reinterpret_cast<const uint2*>(P.m + (size_t)rb * 16) + t); }
    epilogue_group(W, rbf_pair(da * 0x10001u, W.cen), rbf_pair(db * 0x10001u, W.cen), ma, mb,
                   pack_bf16(lo.x, lo.y), pack_bf16(hi.x, hi.y), pack_bf16(lo.z, lo.w), pack_bf16(hi.z, hi.w));
    if (ra < P.E) reinterpret_cast<uint2*>(P.out + (size_t)ra * 16)[t] = ma;
    if (rb < P.E) reinterpret_cast<uint2*>(P.out + (size_t)rb * 16)[t] = mb;
}

}

extern "C" void kernel_launch(void* const* d_in, const int* in_sizes, int n_in, void* d_out, int out_size) {
    using namespace gem;
    Params P;
    P.m = (const __nv_bfloat16*)d_in[0];
    P.idx_in = (const int*)d_in[1];
    P.idx_out = (const int*)d_in[2];
    P.dist = (const __nv_bfloat16*)d_in[3];
    P.angle = (const __nv_bfloat16*)d_in[4];
    P.centers = (const __nv_bfloat16*)d_in[5];
    P.freq = (const __nv_bfloat16*)d_in[6];
    P.w_rbf = (const __nv_bfloat16*)d_in[7];
    P.w_sbf = (const __nv_bfloat16*)d_in[8];
    P.w_down = (const __nv_bfloat16*)d_in[9];
    P.w_up = (const __nv_bfloat16*)d_in[10];
    P.out = (__nv_bfloat16*)d_out;
    P.E = in_sizes[3];
    P.T = in_sizes[1];
    P.G = (P.E + RPB - 1) / RPB;
    {
        const int per = (P.T + P.G - 1) / P.G;
        P.ts[0] = ((long long)per * W0 / 1000 + 63) & ~63;
        P.ts[1] = ((long long)per * W1 / 1000 + 63) & ~63;
        P.ts[2] = (max(per - P.ts[0] - P.ts[1], 0) + 63) & ~63;
        P.t0[0] = 0; P.t0[1] = P.G * P.ts[0]; P.t0[2] = P.t0[1] + P.G * P.ts[1];
    }
    P.zero = 0;

    static int resident = -1;
    static CUtensorMap map;
    if (resident < 0) {
        int dev = 0, sms = 0, occ = 0;
        cudaGetDevice(&dev);
        cudaDeviceGetAttribute(&sms, cudaDevAttrMultiProcessorCount, dev);
        cudaFuncSetAttribute(fused_kernel, cudaFuncAttributeMaxDynamicSharedMemorySize, SM_TOTAL);
        cudaOccupancyMaxActiveBlocksPerMultiprocessor(&occ, fused_kernel, NTHR, SM_TOTAL);
        resident = sms * occ;
        typedef CUresult (*EncodeFn)(CUtensorMap*, CUtensorMapDataType, cuuint32_t, void*, const cuuint64_t*, const cuuint64_t*,
                                     const cuuint32_t*, const cuuint32_t*, CUtensorMapInterleave, CUtensorMapSwizzle,
                                     CUtensorMapL2promotion, CUtensorMapFloatOOBfill);
        void* fn = nullptr; void* cells = nullptr;
        cudaDriverEntryPointQueryResult qr;
        cudaGetDriverEntryPoint("cuTensorMapEncodeTiled", &fn, cudaEnableDefault, &qr);
        cudaGetSymbolAddress(&cells, g_cells);
        const cuuint64_t dims[3] = {CELLB / 4, MAXG, NC * MAXG}, strides[2] = {CELLB, (cuuint64_t)MAXG * CELLB};
        const cuuint32_t box[3] = {CELLB / 4, 1, MAXG}, elem[3] = {1, 1, 1};
        if (!fn || ((EncodeFn)fn)(&map, CU_TENSOR_MAP_DATA_TYPE_UINT32, 3, cells, dims, strides, box, elem, CU_TENSOR_MAP_INTERLEAVE_NONE,
                                  CU_TENSOR_MAP_SWIZZLE_NONE, CU_TENSOR_MAP_L2_PROMOTION_NONE, CU_TENSOR_MAP_FLOAT_OOB_FILL_NONE) != CUDA_SUCCESS)
            resident = 0;
    }

    static cudaTextureObject_t mtex = 0;
    static const void* mptr = nullptr; static int mrows = 0;
    if (mptr != P.m || mrows != P.E) {
        if (mtex) cudaDestroyTextureObject(mtex);
        cudaResourceDesc rd = {};
        rd.resType = cudaResourceTypeLinear;
        rd.res.linear.devPtr = const_cast<__nv_bfloat16*>(P.m);
        rd.res.linear.desc = cudaCreateChannelDesc(32, 32, 0, 0, cudaChannelFormatKindUnsigned);
        rd.res.linear.sizeInBytes = (size_t)P.E * 32;
        cudaTextureDesc td = {};
        td.readMode = cudaReadModeElementType;
        if (cudaCreateTextureObject(&mtex, &rd, &td, nullptr) != cudaSuccess) { mtex = 0; cudaGetLastError(); }
        mptr = P.m; mrows = P.E;
    }
    P.mtex = mtex;

    if (P.G <= MAXG && P.G <= resident && P.T <= OVFCAP && mtex && ((uintptr_t)P.dist & 15u) == 0) {
        fused_kernel<<<P.G, NTHR, SM_TOTAL>>>(P, map);
    } else {
        fb_zero<<<1024, 256>>>(P.G * RPB * 16);
        fb_scatter<<<2048, 256>>>(P);
        fb_epilogue<<<((P.E + 15) / 16 * 32 + 255) / 256, 256>>>(P);
    }
}
```
